```python
import torch

def _softmax(x, axis=-1):
    return torch.softmax(x, dim=axis)
def _gelu(x):
    return torch.nn.functional.gelu(x, approximate="tanh")
def _silu(x):
    return torch.nn.functional.silu(x)
def _sigmoid(x):
    return torch.sigmoid(x)
def _layernorm(x, axis=-1, eps=1e-5):
    m = x.mean(dim=axis, keepdim=True)
    v = x.var(dim=axis, keepdim=True, unbiased=False)
    return (x - m) / torch.sqrt(v + eps)
def _scatter_add(tgt, idx, src, axis=0):
    return tgt.clone().index_add_(axis, idx, src)
def _segment_sum(src, seg, n):
    out = torch.zeros((n,) + src.shape[1:], dtype=src.dtype)
    return out.index_add_(0, seg, src)
def _pad(x, pw):
    flat = tuple(v for pair in reversed(pw) for v in pair)
    return torch.nn.functional.pad(x, flat)

kernel_name = 'standalone__deep_cross_xdeepfm__recsys'

def setup_inputs():

    _w = (lambda a: (lambda t: t.to(torch.bfloat16) if t.is_floating_point() else t)(torch.as_tensor(a)))
    B, F, D, L = 4096, 26, 16, 6
    V = min(1000, 100000)
    Din = F * D
    return {
        "idx": _w((lambda lo, hi, *s: torch.randint(lo, hi, s))(0, V, B, F).to(torch.int64)),
        "table": _w((lambda *s: torch.randn(*s, dtype=torch.bfloat16) * 0.8)(V, D)),
        "ws_cin": _w((lambda *s: torch.randn(*s, dtype=torch.bfloat16) * 0.4)(L, F, F, F) * (1.0 / F)),
        "w_cin_out": _w((lambda *s: torch.randn(*s, dtype=torch.bfloat16) * 0.4)(L * F) * ((L * F) ** -0.5)),
        "w_dnn1": _w((lambda *s: torch.randn(*s, dtype=torch.bfloat16) * 0.8)(Din, Din) * (Din ** -0.5)),
        "b_dnn1": _w((lambda *s: torch.randn(*s, dtype=torch.bfloat16) * 3.2)(Din) * 0.1),
        "w_dnn2": _w((lambda *s: torch.randn(*s, dtype=torch.bfloat16) * 0.4)(Din) * (Din ** -0.5)),
        "b_out": _w((lambda *s: torch.randn(*s, dtype=torch.bfloat16) * 0.4)(1)),
    }

def reference(idx, table, ws_cin, w_cin_out, w_dnn1, b_dnn1, w_dnn2, b_out):
    x0 = table[idx]
    B = x0.shape[0]
    L = ws_cin.shape[0]
    xk = x0
    pooled = []
    for l in range(L):
        xk = torch.einsum('bid,bjd,hij->bhd', xk, x0, ws_cin[l])
        pooled.append(xk.sum(axis=-1))
    p_plus = torch.stack(pooled, axis=1).reshape(B, -1)
    logit_cin = p_plus @ w_cin_out
    h = x0.reshape(B, -1)
    h = _gelu(h @ w_dnn1 + b_dnn1)
    logit_dnn = h @ w_dnn2
    return logit_cin + logit_dnn + b_out
```

```cpp
#include <cuda_runtime.h>
#include <cuda_bf16.h>
#include <cuda.h>
#include <stdint.h>

namespace {

constexpr int NB = 4096, NF = 26;
constexpr int NCTA = 128, NTHR = 512;

constexpr int WL_STEPS = 43, WL_BYTES = WL_STEPS * 1024;
constexpr int WQ_STEPS = 25, WQ_STEP = 1792, WQ_BYTES = WQ_STEPS * WQ_STEP;
constexpr int OFF_L2 = 0;
constexpr int OFF_L3 = WL_BYTES;
constexpr int OFF_Q = 3 * WL_BYTES;
constexpr int IMG_BYTES = OFF_Q + WQ_BYTES;
constexpr int OFF_TAB = 177152;
constexpr int OFF_IDX = OFF_TAB + 32768;
constexpr int OFF_BAR = OFF_IDX + 13312;
constexpr int OFF_W2 = OFF_BAR + 32 * 8;
constexpr int OFF_RES = OFF_W2 + 52 * 8;
constexpr int SMEM_BYTES = OFF_RES + 256;
constexpr int W1_STEP = 3328, W1_BYTES = 26 * W1_STEP;
constexpr int OFF_W1 = OFF_L3;
constexpr int OFF_RAW = OFF_Q;
constexpr int OFF_PU = OFF_Q + 35328;
constexpr int OFF_PW = OFF_PU + 2720;
constexpr int OFF_PC = OFF_PW + 2720;
constexpr int BAR_X = 0;
constexpr int BAR_RAW = 1;
constexpr int BAR_W1 = 2;
constexpr int BAR_Q = 6;
constexpr int BAR_L2 = 9;
constexpr int QCH0 = 5, QCH1 = 15;
static_assert(OFF_TAB % 1024 == 0 && W1_BYTES <= 2 * WL_BYTES, "layout");
static_assert(SMEM_BYTES <= 232448, "smem");

__device__ __align__(1024) uint4 g_img[(IMG_BYTES + 4 * W1_BYTES) / 16];
__device__ __align__(128) unsigned g_cnt[2 * 32 * 32];
__device__ unsigned long long g_xchg[NB * 4];

__device__ __forceinline__ uint32_t smem_u32(const void* p) { return (uint32_t)__cvta_generic_to_shared(p); }
__device__ __forceinline__ void mbar_init(uint32_t bar, uint32_t cnt) {
  asm volatile("mbarrier.init.shared::cta.b64 [%0], %1;" ::"r"(bar), "r"(cnt) : "memory");
}
__device__ __forceinline__ void mbar_expect_tx(uint32_t bar, uint32_t bytes) {
  asm volatile("mbarrier.arrive.expect_tx.shared::cta.b64 _, [%0], %1;" ::"r"(bar), "r"(bytes) : "memory");
}
__device__ __forceinline__ void mbar_arrive(uint32_t bar) {
  asm volatile("mbarrier.arrive.shared::cta.b64 _, [%0];" ::"r"(bar) : "memory");
}
__device__ __forceinline__ void mbar_wait(uint32_t bar, uint32_t parity) {
  asm volatile(
      "{\n"
      ".reg .pred p;\n"
      "WAIT_%=:\n"
      "mbarrier.try_wait.parity.shared::cta.b64 p, [%0], %1;\n"
      "@p bra DONE_%=;\n"
      "bra WAIT_%=;\n"
      "DONE_%=:\n"
      "}\n" ::"r"(bar), "r"(parity) : "memory");
}
__device__ __forceinline__ void bulk_load(uint32_t dst, const void* src, uint32_t bytes, uint32_t bar) {
  asm volatile("cp.async.bulk.shared::cluster.global.mbarrier::complete_tx::bytes [%0], [%1], %2, [%3];" ::"r"(dst),
               "l"(src), "r"(bytes), "r"(bar) : "memory");
}
__device__ __forceinline__ void tma_load_2d(uint32_t dst, const CUtensorMap* tm, int c0, int c1, uint32_t bar) {
  asm volatile("cp.async.bulk.tensor.2d.shared::cluster.global.mbarrier::complete_tx::bytes [%0], [%1, {%3, %4}], [%2];" ::"r"(dst),
               "l"(tm), "r"(bar), "r"(c0), "r"(c1) : "memory");
}
__device__ __forceinline__ void bar_sync(int id, int n) { asm volatile("bar.sync %0, %1;" ::"r"(id), "r"(n) : "memory"); }
__device__ __forceinline__ void wg_fence() { asm volatile("wgmma.fence.sync.aligned;\n" ::: "memory"); }
__device__ __forceinline__ void wg_commit() { asm volatile("wgmma.commit_group.sync.aligned;\n" ::: "memory"); }
template <int N> __device__ __forceinline__ void wg_wait() { asm volatile("wgmma.wait_group.sync.aligned %0;\n" ::"n"(N) : "memory"); }
template <int N> __device__ __forceinline__ void fence_regs(float (&a)[N]) {
#pragma unroll
  for (int i = 0; i < N; i++) asm volatile("" : "+f"(a[i])::"memory");
}
__device__ __forceinline__ uint64_t make_desc(uint32_t addr, uint32_t lbo, uint32_t sbo, uint32_t swz) {
  return (uint64_t)((addr & 0x3FFFF) >> 4) | ((uint64_t)(lbo >> 4) << 16) | ((uint64_t)(sbo >> 4) << 32) | ((uint64_t)swz << 62);
}
__device__ __forceinline__ uint32_t mul_lo(uint32_t x, uint32_t p) {
  uint32_t r;
  asm("{\n.reg .b16 lo, hi;\n.reg .b32 d;\nmov.b32 {lo, hi}, %1;\nmov.b32 d, {lo, lo};\nmul.rn.bf16x2 %0, d, %2;\n}\n" : "=r"(r) : "r"(x), "r"(p));
  return r;
}
__device__ __forceinline__ uint32_t mul_hi(uint32_t x, uint32_t p) {
  uint32_t r;
  asm("{\n.reg .b16 lo, hi;\n.reg .b32 d;\nmov.b32 {lo, hi}, %1;\nmov.b32 d, {hi, hi};\nmul.rn.bf16x2 %0, d, %2;\n}\n" : "=r"(r) : "r"(x), "r"(p));
  return r;
}
__device__ __forceinline__ uint32_t mul2(uint32_t x, uint32_t p) {
  uint32_t r;
  asm("mul.rn.bf16x2 %0, %1, %2;" : "=r"(r) : "r"(x), "r"(p));
  return r;
}
__device__ __forceinline__ uint32_t pack_bf16(float lo, float hi) {
  uint32_t r;
  asm("cvt.rn.bf16x2.f32 %0, %1, %2;" : "=r"(r) : "f"(hi), "f"(lo));
  return r;
}
__device__ __forceinline__ float bf_lo(uint32_t v) { return __uint_as_float(v << 16); }
__device__ __forceinline__ float bf_hi(uint32_t v) { return __uint_as_float(v & 0xffff0000u); }
__device__ __forceinline__ float bf_ld(const __nv_bfloat16* p) { return __uint_as_float((uint32_t)__ldg((const unsigned short*)p) << 16); }
__device__ __forceinline__ void ldsm_x4_t(uint32_t& r0, uint32_t& r1, uint32_t& r2, uint32_t& r3, uint32_t addr) {
  asm volatile("ldmatrix.sync.aligned.m8n8.x4.trans.shared.b16 {%0,%1,%2,%3}, [%4];" : "=r"(r0), "=r"(r1), "=r"(r2), "=r"(r3) : "r"(addr) : "memory");
}
__device__ __forceinline__ void ldsm_x4(uint32_t& r0, uint32_t& r1, uint32_t& r2, uint32_t& r3, uint32_t addr) {
  asm volatile("ldmatrix.sync.aligned.m8n8.x4.shared.b16 {%0,%1,%2,%3}, [%4];" : "=r"(r0), "=r"(r1), "=r"(r2), "=r"(r3) : "r"(addr) : "memory");
}
__device__ __forceinline__ float tanh_fast(float x) {
  float y;
  asm("tanh.approx.f32 %0, %1;" : "=f"(y) : "f"(x));
  return y;
}


__device__ __forceinline__ bool l_slot_dec(int t, int q, int& i, int& b) {
  const bool m = t < 78;
  const int ce = t / 13;
  i = m ? 8 * (ce >> 1) + (ce & 1) + 2 * q : 24 + (q >> 1);
  b = (m ? t - 13 * ce : 2 * (t - 78)) + q;
  b = b >= 13 ? b - 13 : b;
  return t < 85 && !(t == 84 && (q & 1));
}
__device__ __forceinline__ int q_slot_dec(int t, int q, int& p, int& b, bool& sym) {
  const bool m = t < 42;
  const int s3 = t / 14, r = t - 14 * s3, e = r >= 7 ? 1 : 0, dl = r - 7 * e;
  p = m ? 8 * s3 + 2 * q + e : 24 + (q & 1);
  b = (m ? 4 * s3 + dl : (t < 44 ? t - 31 : (t < 46 ? t - 42 : 4 * (t - 46)))) + q;
  b = b >= 13 ? b - 13 : b;
  sym = m ? dl != 0 : b != 12;
  return m ? 1 : (t < 46 ? ((b == 12 || b <= 5) ? 1 : 0) : (t < 49 || q == 0 ? 2 : (q == 1 ? 3 : 0)));
}

__device__ __forceinline__ uint32_t q_frag(int t, uint32_t E, uint32_t O, const uint32_t (&P)[13]) {
  if (t < 42) {
    int s3 = t / 14, e = (t / 7) % 2, dl = t % 7;
    int a = 4 * s3, b = (4 * s3 + dl) % 13;
    return e ? mul_hi(P[a], P[b]) : mul_lo(P[a], P[b]);
  } else if (t < 46) {
    int j = (t == 42) ? 11 : (t == 43) ? 12 : (t == 44) ? 2 : 3;
    return mul2(E, P[j]);
  } else if (t < 49) {
    return P[4 * (t - 46)];
  }
  return O;
}

template <int SCALE_D, int DOFF>
__device__ __forceinline__ void wgmma_rs_n32(float (&d)[16], uint32_t a0, uint32_t a1, uint32_t a2, uint32_t a3, uint64_t descB) {
  asm volatile(
      "{\n.reg .b64 dsc;\nadd.s64 dsc, %20, %22;\n"
      "wgmma.mma_async.sync.aligned.m64n32k16.f32.bf16.bf16 "
      "{%0, %1, %2, %3, %4, %5, %6, %7, %8, %9, %10, %11, %12, %13, %14, %15}, "
      "{%16, %17, %18, %19}, dsc, %21, 1, 1, 0;\n}\n"
      : "+f"(d[0]), "+f"(d[1]), "+f"(d[2]), "+f"(d[3]), "+f"(d[4]), "+f"(d[5]), "+f"(d[6]), "+f"(d[7]), "+f"(d[8]), "+f"(d[9]), "+f"(d[10]), "+f"(d[11]), "+f"(d[12]), "+f"(d[13]), "+f"(d[14]), "+f"(d[15])
      : "r"(a0), "r"(a1), "r"(a2), "r"(a3), "l"(descB), "n"(SCALE_D), "n"(DOFF));
}

template <int SCALE_D, int DOFF>
__device__ __forceinline__ void wgmma_rs_n56(float (&d)[28], uint32_t a0, uint32_t a1, uint32_t a2, uint32_t a3, uint64_t descB) {
  asm volatile(
      "{\n.reg .b64 dsc;\nadd.s64 dsc, %32, %34;\n"
      "wgmma.mma_async.sync.aligned.m64n56k16.f32.bf16.bf16 "
      "{%0, %1, %2, %3, %4, %5, %6, %7, %8, %9, %10, %11, %12, %13, %14, %15, %16, %17, %18, %19, %20, %21, %22, %23, %24, %25, %26, %27}, "
      "{%28, %29, %30, %31}, dsc, %33, 1, 1, 0;\n}\n"
      : "+f"(d[0]), "+f"(d[1]), "+f"(d[2]), "+f"(d[3]), "+f"(d[4]), "+f"(d[5]), "+f"(d[6]), "+f"(d[7]), "+f"(d[8]), "+f"(d[9]), "+f"(d[10]), "+f"(d[11]), "+f"(d[12]), "+f"(d[13]), "+f"(d[14]), "+f"(d[15]), "+f"(d[16]), "+f"(d[17]), "+f"(d[18]), "+f"(d[19]), "+f"(d[20]), "+f"(d[21]), "+f"(d[22]), "+f"(d[23]), "+f"(d[24]), "+f"(d[25]), "+f"(d[26]), "+f"(d[27])
      : "r"(a0), "r"(a1), "r"(a2), "r"(a3), "l"(descB), "n"(SCALE_D), "n"(DOFF));
}

template <int SCALE_D, int DOFF>
__device__ __forceinline__ void wgmma_rs_n104_tb(float (&d)[52], uint32_t a0, uint32_t a1, uint32_t a2, uint32_t a3, uint64_t descB) {
  asm volatile(
      "{\n.reg .b64 dsc;\nadd.s64 dsc, %56, %58;\n"
      "wgmma.mma_async.sync.aligned.m64n104k16.f32.bf16.bf16 "
      "{%0, %1, %2, %3, %4, %5, %6, %7, %8, %9, %10, %11, %12, %13, %14, %15, %16, %17, %18, %19, %20, %21, %22, %23, %24, %25, %26, %27, %28, %29, %30, %31, %32, %33, %34, %35, %36, %37, %38, %39, %40, %41, %42, %43, %44, %45, %46, %47, %48, %49, %50, %51}, "
      "{%52, %53, %54, %55}, dsc, %57, 1, 1, 1;\n}\n"
      : "+f"(d[0]), "+f"(d[1]), "+f"(d[2]), "+f"(d[3]), "+f"(d[4]), "+f"(d[5]), "+f"(d[6]), "+f"(d[7]), "+f"(d[8]), "+f"(d[9]), "+f"(d[10]), "+f"(d[11]), "+f"(d[12]), "+f"(d[13]), "+f"(d[14]), "+f"(d[15]), "+f"(d[16]), "+f"(d[17]), "+f"(d[18]), "+f"(d[19]), "+f"(d[20]), "+f"(d[21]), "+f"(d[22]), "+f"(d[23]), "+f"(d[24]), "+f"(d[25]), "+f"(d[26]), "+f"(d[27]), "+f"(d[28]), "+f"(d[29]), "+f"(d[30]), "+f"(d[31]), "+f"(d[32]), "+f"(d[33]), "+f"(d[34]), "+f"(d[35]), "+f"(d[36]), "+f"(d[37]), "+f"(d[38]), "+f"(d[39]), "+f"(d[40]), "+f"(d[41]), "+f"(d[42]), "+f"(d[43]), "+f"(d[44]), "+f"(d[45]), "+f"(d[46]), "+f"(d[47]), "+f"(d[48]), "+f"(d[49]), "+f"(d[50]), "+f"(d[51])
      : "r"(a0), "r"(a1), "r"(a2), "r"(a3), "l"(descB), "n"(SCALE_D), "n"(DOFF));
}


template <int S> __device__ __forceinline__ void q_step(float (&acc)[28], const uint32_t (&a)[4], uint64_t desc) {
  wgmma_rs_n56<(S > 0 ? 1 : 0), S * (WQ_STEP / 16)>(acc, a[0], a[1], a[2], a[3], desc);
}
constexpr int GQ = 2;
template <int S0, int NS> struct QLoop {
  static __device__ __forceinline__ void run(float (&acc)[28], const uint32_t (&P0)[13], const uint32_t (&P1)[13], uint32_t E0,
                                             uint32_t E1, uint32_t O0, uint32_t O1, uint64_t desc, uint32_t barq) {
    constexpr int GG = (S0 + GQ <= NS) ? GQ : (NS - S0);
    uint32_t a[GG][4];
#pragma unroll
    for (int g = 0; g < GG; g++) {
      const int s = S0 + g;
      a[g][0] = q_frag(2 * s, E0, O0, P0);
      a[g][1] = q_frag(2 * s, E1, O1, P1);
      a[g][2] = q_frag(2 * s + 1, E0, O0, P0);
      a[g][3] = q_frag(2 * s + 1, E1, O1, P1);
    }
    if (S0 == 0) mbar_wait(barq, 0);
    if (S0 <= QCH0 && S0 + GG > QCH0) mbar_wait(barq + 8, 0);
    if (S0 <= QCH1 && S0 + GG > QCH1) mbar_wait(barq + 16, 0);
    wg_fence();
    q_step<S0>(acc, a[0], desc);
    if constexpr (GG > 1) q_step<S0 + 1>(acc, a[1 % GG], desc);
    wg_commit();
    if constexpr (S0 + GG < NS) {
      wg_wait<1>();
      QLoop<S0 + GG, NS>::run(acc, P0, P1, E0, E1, O0, O1, desc, barq);
    }
  }
};
__device__ __forceinline__ uint32_t l_frag(int t, const uint32_t (&X)[4], const uint32_t (&P)[13]) {
  if (t < 78) {
    const int ce = t / 13, j = t % 13, c = ce / 2, e = ce % 2;
    return e ? mul_hi(X[c], P[j]) : mul_lo(X[c], P[j]);
  } else if (t < 85) {
    return mul_lo(X[3], P[2 * (t - 78)]);
  }
  return 0u;
}
constexpr int GL = 4;
template <int S0> struct LLoop {
  static __device__ __forceinline__ void run(float (&acc)[16], const uint32_t (&X0)[4], const uint32_t (&X1)[4],
                                             const uint32_t (&P0)[13], const uint32_t (&P1)[13], uint64_t desc) {
    constexpr int GG = (S0 + GL <= WL_STEPS) ? GL : (WL_STEPS - S0);
    uint32_t a[GG][4];
#pragma unroll
    for (int g = 0; g < GG; g++) {
      const int s = S0 + g;
      a[g][0] = l_frag(2 * s, X0, P0);
      a[g][1] = l_frag(2 * s, X1, P1);
      a[g][2] = l_frag(2 * s + 1, X0, P0);
      a[g][3] = l_frag(2 * s + 1, X1, P1);
    }
    wg_fence();
    wgmma_rs_n32<(S0 > 0 ? 1 : 0), S0 * 64>(acc, a[0][0], a[0][1], a[0][2], a[0][3], desc);
    if constexpr (GG > 1) wgmma_rs_n32<1, (S0 + 1) * 64>(acc, a[1 % GG][0], a[1 % GG][1], a[1 % GG][2], a[1 % GG][3], desc);
    if constexpr (GG > 2) wgmma_rs_n32<1, (S0 + 2) * 64>(acc, a[2 % GG][0], a[2 % GG][1], a[2 % GG][2], a[2 % GG][3], desc);
    if constexpr (GG > 3) wgmma_rs_n32<1, (S0 + 3) * 64>(acc, a[3 % GG][0], a[3 % GG][1], a[3 % GG][2], a[3 % GG][3], desc);
    wg_commit();
    if constexpr (S0 + GG < WL_STEPS) {
      wg_wait<1>();
      LLoop<S0 + GG>::run(acc, X0, X1, P0, P1, desc);
    }
  }
};

__device__ __forceinline__ void wait_count(const unsigned* cnt, unsigned epoch, int lane) {
  unsigned cur;
  int it = 0;
  do {
    asm volatile("ld.relaxed.gpu.global.u32 %0, [%1];" : "=r"(cur) : "l"(cnt + lane * 32) : "memory");
  } while ((int)(cur - 4 * epoch) < 0 && ++it < (1 << 20));
  __syncwarp();
  asm volatile("fence.proxy.async.global;" ::: "memory");
}
__device__ __forceinline__ void st_img32(char* p, uint32_t v) { *reinterpret_cast<uint32_t*>(p) = v; }
__device__ __forceinline__ void st_img128(char* p, uint4 v) { *reinterpret_cast<uint4*>(p) = v; }
__device__ __forceinline__ bool elect_one() {
  uint32_t p;
  asm volatile("{\n.reg .pred P;\nelect.sync _|P, 0xffffffff;\nselp.u32 %0, 1, 0, P;\n}\n" : "=r"(p));
  return p != 0;
}
__device__ __forceinline__ uint32_t tab_addr(uint32_t v, uint32_t base_h) {
  const uint32_t o = v * 32 + base_h;
  return o ^ ((o >> 3) & 0x70);
}
__device__ __forceinline__ uint32_t lds32(uint32_t addr) {
  uint32_t v;
  asm volatile("ld.shared.b32 %0, [%1];" : "=r"(v) : "r"(addr) : "memory");
  return v;
}
constexpr int NPRE = 10;
template <int G> struct DnnLoop {
  static __device__ __forceinline__ void run(float (&acc)[52], uint32_t (&A)[NPRE][4], uint64_t desc, uint32_t bars, uint32_t ia,
                                             uint32_t tb) {
    constexpr int r0 = (2 * G) % NPRE, r1 = (2 * G + 1) % NPRE;
    if (G == 0 || G == 1 || G == 4 || G == 8) mbar_wait(bars + (BAR_W1 + (G >= 1) + (G >= 4) + (G >= 8)) * 8, 0);
    wg_fence();
    wgmma_rs_n104_tb<1, 2 * G * (W1_STEP / 16)>(acc, A[r0][0], A[r0][1], A[r0][2], A[r0][3], desc);
    wgmma_rs_n104_tb<1, (2 * G + 1) * (W1_STEP / 16)>(acc, A[r1][0], A[r1][1], A[r1][2], A[r1][3], desc);
    wg_commit();
    if constexpr (G >= 1) {
      wg_wait<1>();
      constexpr int f0 = 2 * (G - 1) + NPRE, f1 = f0 + 1, q0 = f0 % NPRE, q1 = f1 % NPRE;
      if constexpr (f0 < 26) ldsm_x4(A[q0][0], A[q0][1], A[q0][2], A[q0][3], tab_addr(lds32(ia + f0 * 4), tb));
      if constexpr (f1 < 26) ldsm_x4(A[q1][0], A[q1][1], A[q1][2], A[q1][3], tab_addr(lds32(ia + f1 * 4), tb));
    }
    if constexpr (G + 1 < 13) DnnLoop<G + 1>::run(acc, A, desc, bars, ia, tb);
  }
};

__device__ __forceinline__ void load_p(uint32_t (&P0)[13], uint32_t (&P1)[13], uint32_t& E0, uint32_t& E1, uint32_t i0, uint32_t i5,
                                       uint32_t i6, uint32_t tb) {
#pragma unroll
  for (int t = 0; t < 5; t++) ldsm_x4_t(P0[2 * t], P1[2 * t], P0[2 * t + 1], P1[2 * t + 1], tab_addr(lds32(i0 + t * 16), tb));
  ldsm_x4_t(P0[10], P1[10], P0[11], P1[11], tab_addr(lds32(i5), tb));
  ldsm_x4_t(P0[12], P1[12], E0, E1, tab_addr(lds32(i6), tb));
}

struct Scratch { char* img; unsigned* cnt; unsigned long long* xchg; };

__global__ void __launch_bounds__(NTHR, 1)
xdeepfm_kernel(const __nv_bfloat16* __restrict__ ws, const __nv_bfloat16* __restrict__ wc, const int* __restrict__ idx,
               const Scratch scr, const __nv_bfloat16* __restrict__ w1, const __nv_bfloat16* __restrict__ b1,
               const __nv_bfloat16* __restrict__ w2, const __nv_bfloat16* __restrict__ bout, __nv_bfloat16* __restrict__ out,
               const __grid_constant__ CUtensorMap tmtab) {
  extern __shared__ __align__(1024) uint8_t smem[];
  const int tid = threadIdx.x;
  const int cta = blockIdx.x;
  const uint32_t sb = smem_u32(smem);
  const uint32_t* ws32 = reinterpret_cast<const uint32_t*>(ws);
  const unsigned short* wc16 = reinterpret_cast<const unsigned short*>(wc);
  const int warp = __shfl_sync(0xffffffffu, tid >> 5, 0);
  const int lane = tid & 31;
  const int wg = warp >> 2;
  if (tid == 448) asm volatile("prefetch.tensormap [%0];" ::"l"(&tmtab) : "memory");
  const int mem = cta & 3;
  const int grpbase = (cta >> 2) * 128;
  const uint32_t bars = sb + OFF_BAR;
  const int lu = cta < 104 ? 5 : (cta < 108 ? 0 : (cta < 110 ? cta - 107 : -1));
  const int gi = cta >> 2;
  const uint32_t rawoff = (uint32_t)(reinterpret_cast<uintptr_t>(ws) + lu * 35152) & 127u;
  if (warp == 7) {
    if (elect_one()) {
      mbar_init(bars + BAR_RAW * 8, 1);
      mbar_init(bars + BAR_X * 8, 1);
      asm volatile("fence.mbarrier_init.release.cluster;" ::: "memory");
      if (lu >= 0) {
        mbar_expect_tx(bars + BAR_RAW * 8, 35152);
#pragma unroll 1
        for (int j = 0; j < 4; j++)
          bulk_load(sb + OFF_RAW + rawoff + j * 8832, reinterpret_cast<const char*>(ws) + lu * 35152 + j * 8832, j < 3 ? 8832 : 35152 - 3 * 8832,
                    bars + BAR_RAW * 8);
      } else {
        mbar_arrive(bars + BAR_RAW * 8);
      }
    }
    __syncwarp();
  } else if (lane == 0 && warp >= 6) {
    if (warp == 15) {
#pragma unroll 1
      for (int j = 0; j < 4; j++) mbar_init(bars + (BAR_W1 + j) * 8, 1);
    } else if (warp >= 8 && warp < 14) {
      mbar_init(bars + (warp - 2) * 8, 1);
    }
    asm volatile("fence.mbarrier_init.release.cluster;" ::: "memory");
  }
  __syncwarp();
  if (wg < 2) asm volatile("bar.arrive 0, 512;" ::: "memory");
  uint4 w1v = make_uint4(0, 0, 0, 0);
  const int w1j = tid - 288;
  const bool doW1 = cta < 104 && w1j >= 0 && w1j < 208;
  const int w1k = w1j / 13, w1g = w1j - 13 * w1k;
  if (doW1) w1v = __ldg(reinterpret_cast<const uint4*>(w1) + ((cta % 26) * 16 + w1k) * 52 + (cta / 26) * 13 + w1g);
  float* PU = reinterpret_cast<float*>(smem + OFF_PU);
  float* PW = reinterpret_cast<float*>(smem + OFF_PW);
  float* PC = reinterpret_cast<float*>(smem + OFF_PC);
  uint32_t gv0 = 0, gv1 = 0, gv2 = 0, gv3 = 0, goff = 0;
  bool gstore = false;
  if (wg < 2) {
    if (lu >= 0) {
      if (tid < 169) {
        const int h = tid / 13, jp = tid - 13 * h;
        gv0 = (h == 2 * jp ? 0x3F80u : 0u) | (h == 2 * jp + 1 ? 0x3F800000u : 0u);
        gv1 = (h + 13 == 2 * jp ? 0x3F80u : 0u) | (h + 13 == 2 * jp + 1 ? 0x3F800000u : 0u);
        if (cta < 104) {
          gv0 = __ldg(ws32 + 4 * 8788 + h * 338 + gi * 13 + jp);
          gv1 = __ldg(ws32 + 4 * 8788 + (h + 13) * 338 + gi * 13 + jp);
        }
      } else if (warp == 6) {
        if (cta < 104 && lane < 27) gv0 = __ldg(wc16 + (lane < 26 ? 4 * 26 + lane : 3 * 26 + gi));
      } else if (warp == 7) {
        if (lane < 26) gv0 = __ldg(wc16 + lu * 26 + lane);
      }
    }
  } else if (warp < 10) {
    const int id = cta * 64 + tid - 256, q = id & 3, ci = (id >> 2) & 31, t = id >> 7;
    const int n = ci < 24 ? ci : (ci < 28 ? 2 * ci : 55);
    const int h = ci < 24 ? ci : 24 + ((ci - 24) >> 1);
    int p, b; bool sym;
    const bool v = q_slot_dec(t, q, p, b, sym) == 1 && ci < 28 && t < 50;
    gstore = ci < 29 && t < 50;
    goff = OFF_Q + (t >> 1) * WQ_STEP + (n >> 3) * 256 + (t & 1) * 128 + (n & 7) * 16 + q * 4;
    if (v) {
      gv0 = __ldg(ws32 + h * 338 + p * 13 + b);
      if (sym) {
        const unsigned short* w16 = reinterpret_cast<const unsigned short*>(ws) + h * 676 + p + b * 52;
        gv1 = __ldg(w16);
        gv2 = __ldg(w16 + 26);
      }
    }
  } else if (warp < 13) {
    const int id = cta * 96 + tid - 320, u12 = id & 4095, l3 = id >> 12;
    const int n = ((u12 >> 4) & 3) * 8 + (u12 & 7), t = 2 * (u12 >> 6) + ((u12 >> 3) & 1);
    const int h = n < 24 ? n : 24 + ((n - 24) >> 2);
    const bool hv = n < 24 || !(n & 1);
    const uint32_t* wl = ws32 + (l3 + 1) * 8788 + h * 338;
    int i, b;
    gstore = t < 86 && !(n == 25 && l3 < 2);
    goff = l3 * WL_BYTES + u12 * 16;
    if (l_slot_dec(t, 0, i, b) && hv) gv0 = __ldg(wl + i * 13 + b);
    if (l_slot_dec(t, 1, i, b) && hv) gv1 = __ldg(wl + i * 13 + b);
    if (l_slot_dec(t, 2, i, b) && hv) gv2 = __ldg(wl + i * 13 + b);
    if (l_slot_dec(t, 3, i, b) && hv) gv3 = __ldg(wl + i * 13 + b);
  }
  if (warp != 14) asm volatile("bar.arrive 9, 512;" ::: "memory");
  else {
    bar_sync(9, 512);
    if (elect_one()) {
      mbar_expect_tx(bars + BAR_X * 8, 13312 + 32768);
#pragma unroll 1
      for (int j = 0; j < 2; j++) bulk_load(sb + OFF_IDX + j * 6656, idx + (grpbase + j * 64) * NF, 6656, bars + BAR_X * 8);
#pragma unroll 1
      for (int j = 0; j < 4; j++) tma_load_2d(sb + OFF_TAB + j * 8192, &tmtab, 0, j * 64, bars + BAR_X * 8);
    }
    __syncwarp();
  }
  unsigned cnt0;
  asm volatile("ld.relaxed.gpu.global.u32 %0, [%1];" : "=r"(cnt0) : "l"(scr.cnt + (cta & 31) * 32) : "memory");
  const unsigned epoch = cnt0 / 4 + 1;

  float dacc[52];
  if (wg >= 2) {
    if (warp >= 9) {
      if (doW1) *reinterpret_cast<uint4*>(smem + OFF_W1 + w1g * 256 + w1k * 16) = w1v;
      asm volatile("fence.proxy.async.shared::cta;" ::: "memory");
      if (warp == 13) bar_sync(7, 224); else asm volatile("bar.arrive 7, 224;" ::: "memory");
    }
    if (warp != 13) {
      if (gstore) {
        if (warp < 10)
          st_img32(scr.img + goff, pack_bf16(bf_lo(gv0) + __uint_as_float(gv1 << 16), bf_hi(gv0) + __uint_as_float(gv2 << 16)));
        else
          st_img128(scr.img + goff, make_uint4(gv0, gv1, gv2, gv3));
      }
    }
    if (warp == 13) {
      if (cta < 104 && elect_one()) {
        asm volatile("cp.async.bulk.global.shared::cta.bulk_group [%0], [%1], 3328;" ::"l"(scr.img + IMG_BYTES + cta * W1_STEP), "r"(sb + OFF_W1) : "memory");
        asm volatile("cp.async.bulk.commit_group;" ::: "memory");
        asm volatile("cp.async.bulk.wait_group 0;" ::: "memory");
        asm volatile("red.relaxed.gpu.global.add.u32 [%0], 1;" ::"l"(scr.cnt + 1024 + cta * 8) : "memory");
      }
      __syncwarp();
    }
    bar_sync(0, 512);
    asm volatile("bar.arrive 1, 512;" ::: "memory");
    if (warp == 13) {
      {
        unsigned cur;
        int it = 0;
        const unsigned* cp = scr.cnt + 1024 + (mem * 26 + (lane < 26 ? lane : 0)) * 8;
        do {
          asm volatile("ld.relaxed.gpu.global.u32 %0, [%1];" : "=r"(cur) : "l"(cp) : "memory");
        } while ((int)(cur - epoch) < 0 && ++it < (1 << 20));
        __syncwarp();
        asm volatile("fence.proxy.async.global;" ::: "memory");
      }
      if (elect_one()) {
#pragma unroll 1
        for (int j = 0; j < 4; j++) {
          const int wo = j == 0 ? 0 : (j == 1 ? 2 : (j == 2 ? 8 : 17)), wn = j == 0 ? 2 : (j == 1 ? 6 : 9);
          mbar_expect_tx(bars + (BAR_W1 + j) * 8, wn * W1_STEP);
          bulk_load(sb + OFF_W1 + wo * W1_STEP, scr.img + IMG_BYTES + mem * W1_BYTES + wo * W1_STEP, wn * W1_STEP, bars + (BAR_W1 + j) * 8);
        }
      }
      __syncwarp();
    }
    if (warp == 14) {
#pragma unroll 1
      for (int k = lane; k < 52; k += 32) {
        const uint32_t v = __ldg(reinterpret_cast<const uint32_t*>(w2) + 52 * mem + k);
        *reinterpret_cast<float2*>(smem + OFF_W2 + k * 8) = make_float2(0.5f * bf_lo(v), 0.5f * bf_hi(v));
      }
    }
    {
      const uint32_t* b32 = reinterpret_cast<const uint32_t*>(b1) + 52 * mem + (lane & 3);
#pragma unroll
      for (int c = 0; c < 13; c++) {
        const uint32_t v = __ldg(b32 + 4 * c);
        dacc[4 * c] = dacc[4 * c + 2] = bf_lo(v);
        dacc[4 * c + 1] = dacc[4 * c + 3] = bf_hi(v);
      }
    }
    const int arow = (wg - 2) * 64 + (warp & 3) * 16 + (lane & 15);
    const uint32_t ia = sb + OFF_IDX + arow * (NF * 4);
    const uint32_t tb = sb + OFF_TAB + (lane >> 4) * 16;
    const uint64_t descW = make_desc(__shfl_sync(0xffffffffu, sb, 0) + OFF_W1, 128, 256, 0);
    mbar_wait(bars + BAR_X * 8, 0);
    {
      uint32_t A[NPRE][4];
#pragma unroll
      for (int f = 0; f < NPRE; f++) ldsm_x4(A[f][0], A[f][1], A[f][2], A[f][3], tab_addr(lds32(ia + f * 4), tb));
      DnnLoop<0>::run(dacc, A, descW, bars, ia, tb);
    }
    wg_wait<0>();
    fence_regs(dacc);
    bar_sync(5, 256);
    if (warp == 8) {
      mbar_wait(bars + BAR_Q * 8, 0);
      if (elect_one()) {
#pragma unroll 1
        for (int j = 1; j < 3; j++) {
          mbar_expect_tx(bars + (BAR_L2 + j) * 8, WL_BYTES);
          bulk_load(sb + j * WL_BYTES, scr.img + j * WL_BYTES, WL_BYTES, bars + (BAR_L2 + j) * 8);
        }
      }
      __syncwarp();
    }
  } else {
    if (lu >= 0) {
      if (tid < 169) {
        const int h = tid / 13, jp = tid - 13 * h;
        *reinterpret_cast<float2*>(PW + h * 26 + 2 * jp) = make_float2(bf_lo(gv0), bf_hi(gv0));
        *reinterpret_cast<float2*>(PW + (h + 13) * 26 + 2 * jp) = make_float2(bf_lo(gv1), bf_hi(gv1));
      } else if (warp >= 6) {
        PC[tid - 192] = bf_lo(gv0);
      }
      const int item = tid >> 2, hq = tid & 3;
      const int t = 13 * (cta & 3) + (item >> 2), q = item & 3;
      const bool act = item < 52 && t < 50;
      int p, b; bool sym;
      int ty = q_slot_dec(t, q, p, b, sym);
      if (!act) { ty = 0; p = 0; b = 0; }
      const int n = gi < 24 ? 24 + gi : (gi == 24 ? 49 : (gi == 25 ? 53 : 51));
      const int off = OFF_Q + (t >> 1) * WQ_STEP + (n >> 3) * 256 + (t & 1) * 128 + (n & 7) * 16 + q * 4;
      bar_sync(4, 256);
      mbar_wait(bars + BAR_RAW * 8, 0);
      if (tid < 169) {
        float u0 = 0.f, u1 = 0.f, u2 = 0.f, u3 = 0.f;
        const uint2* raw = reinterpret_cast<const uint2*>(smem + OFF_RAW + rawoff) + tid;
#pragma unroll 1
        for (int h0 = 0; h0 < 26; h0 += 13) {
          uint2 v[13];
#pragma unroll
          for (int h = 0; h < 13; h++) v[h] = raw[(h0 + h) * 169];
#pragma unroll
          for (int h = 0; h < 13; h++) {
            const float c = PC[32 + h0 + h];
            u0 = fmaf(c, bf_lo(v[h].x), u0); u1 = fmaf(c, bf_hi(v[h].x), u1);
            u2 = fmaf(c, bf_lo(v[h].y), u2); u3 = fmaf(c, bf_hi(v[h].y), u3);
          }
        }
        *reinterpret_cast<float4*>(PU + 4 * tid) = make_float4(u0, u1, u2, u3);
      }
      bar_sync(4, 256);
      if (cta < 108) {
        if (warp < 7) {
          float v0 = 0.f, v1 = 0.f;
          const float fs = (ty == 1 && sym) ? 1.f : 0.f, f1 = ty == 1 ? 1.f : 0.f;
#pragma unroll
          for (int k = 0; k < 7; k++) {
            const int h = min(hq + 4 * k, 25);
            const float m = hq + 4 * k < 26 ? 1.f : 0.f;
            const float2 wb = *reinterpret_cast<const float2*>(PW + h * 26 + 2 * b);
            const float2 vv = *reinterpret_cast<const float2*>(PU + h * 26 + 2 * b);
            const float wp = m * f1 * PW[h * 26 + p];
            const float vp = m * (ty == 2 ? PC[h] : fs * PU[h * 26 + p]);
            v0 = fmaf(wp, vv.x, fmaf(wb.x, vp, v0));
            v1 = fmaf(wp, vv.y, fmaf(wb.y, vp, v1));
          }
          if (ty == 3 && hq == 0) v0 = PC[26];
          v0 += __shfl_xor_sync(0xffffffffu, v0, 1); v1 += __shfl_xor_sync(0xffffffffu, v1, 1);
          v0 += __shfl_xor_sync(0xffffffffu, v0, 2); v1 += __shfl_xor_sync(0xffffffffu, v1, 2);
          if (act && hq == 0) st_img32(scr.img + off, pack_bf16(v0, v1));
        }
      } else {
#pragma unroll 1
        for (int it = tid; it < 344; it += 256) {
          const int t2 = it >> 2, q2 = it & 3;
          int i, b2;
          const bool v = l_slot_dec(t2, q2, i, b2);
          const float2 x = *reinterpret_cast<const float2*>(PU + i * 26 + 2 * b2);
          const int o2 = (cta - 108) * WL_BYTES + (t2 >> 1) * 1024 + 3 * 256 + (t2 & 1) * 128 + 16 + q2 * 4;
          st_img32(scr.img + o2, v ? pack_bf16(x.x, x.y) : 0u);
        }
      }
    }
    asm volatile("fence.proxy.async.shared::cta;" ::: "memory");
    bar_sync(1, 512);
    if (warp == 0) {
      if (lane == 0) asm volatile("red.release.gpu.global.add.u32 [%0], 1;" ::"l"(scr.cnt + (cta & 31) * 32) : "memory");
      wait_count(scr.cnt, epoch, lane);
    }
    if (warp == 0 && elect_one()) {
#pragma unroll 1
      for (int j = 0; j < 3; j++) {
        const int qo = j == 0 ? 0 : (j == 1 ? QCH0 : QCH1), qn = j == 0 ? QCH0 : (j == 1 ? QCH1 - QCH0 : WQ_STEPS - QCH1);
        mbar_expect_tx(bars + (BAR_Q + j) * 8, qn * WQ_STEP);
        bulk_load(sb + OFF_Q + qo * WQ_STEP, scr.img + OFF_Q + qo * WQ_STEP, qn * WQ_STEP, bars + (BAR_Q + j) * 8);
      }
      mbar_expect_tx(bars + BAR_L2 * 8, WL_BYTES);
      bulk_load(sb + OFF_L2, scr.img + OFF_L2, WL_BYTES, bars + BAR_L2 * 8);
    }
    __syncwarp();
  }

  {
    const int q = lane & 3;
    const int wq = warp & 3;
    mbar_wait(bars + BAR_X * 8, 0);
    const uint32_t ia = sb + OFF_IDX + (32 * mem + wq) * (NF * 4);
    const int cf = 2 * (lane >> 4) + (lane & 7);
    const uint32_t i0 = ia + cf * 4;
    const uint32_t i5 = ia + (cf < 6 ? 20 + cf : cf - 6) * 4;
    const uint32_t i6 = ia + (lane < 16 ? ((lane & 7) < 2 ? 24 + (lane & 7) : (lane & 7) - 2) : 24 + (lane & 1)) * 4;
    const uint32_t tb = sb + OFF_TAB + ((lane >> 3) & 1) * 16;
    const uint32_t esel = (q & 1) ? 0x3232u : 0x1010u;
    const uint32_t sbu = __shfl_sync(0xffffffffu, sb, 0);
    const uint64_t descQ = make_desc(sbu + OFF_Q, 128, 256, 0);
    const uint64_t descL = make_desc(sbu + OFF_L2, 128, 256, 0);
    float* res = reinterpret_cast<float*>(smem + OFF_RES);
    uint32_t P0[13], P1[13], E0, E1;
    load_p(P0, P1, E0, E1, i0 + wg * (4 * NF * 4), i5 + wg * (4 * NF * 4), i6 + wg * (4 * NF * 4), tb);
    if (wg >= 2) {
      float s0 = 0.f, s1 = 0.f;
      {
        const float2* bw = reinterpret_cast<const float2*>(smem + OFF_W2) + (lane & 3);
        const float k1 = 0.7978845608028654f, k2 = 0.035677408136300125f;
#pragma unroll
        for (int c = 0; c < 13; c++) {
          const float2 w = bw[4 * c];
#pragma unroll
          for (int e = 0; e < 4; e++) {
            const float x = dacc[4 * c + e];
            const float y = fmaf(x, tanh_fast(x * fmaf(x * x, k2, k1)), x);
            if (e < 2) s0 = fmaf(y, (e & 1) ? w.y : w.x, s0);
            else s1 = fmaf(y, (e & 1) ? w.y : w.x, s1);
          }
        }
      }
      s0 += __shfl_xor_sync(0xffffffffu, s0, 1); s0 += __shfl_xor_sync(0xffffffffu, s0, 2);
      s1 += __shfl_xor_sync(0xffffffffu, s1, 1); s1 += __shfl_xor_sync(0xffffffffu, s1, 2);
      if ((lane & 3) < 2) {
        const int row = grpbase + (wg - 2) * 64 + (warp & 3) * 16 + (lane >> 2) + (lane & 1) * 8;
        const unsigned long long tag = (unsigned long long)epoch << 32;
        asm volatile("st.relaxed.gpu.global.u64 [%0], %1;" ::"l"(scr.xchg + row * 4 + mem), "l"(tag | __float_as_uint((lane & 1) ? s1 : s0)) : "memory");
      }
    }
    float sA = 0.f, s = 0.f;
#pragma unroll 1
    for (int tl = 0; tl < 2; tl++) {
      E0 = __byte_perm(E0, 0, esel);
      E1 = __byte_perm(E1, 0, esel);
      const uint32_t O0 = q == 0 ? P0[12] : 0x3F803F80u;
      const uint32_t O1 = q == 0 ? P1[12] : 0x3F803F80u;
      float accq[28];
      QLoop<0, WQ_STEPS>::run(accq, P0, P1, E0, E1, O0, O1, descQ, bars + BAR_Q * 8);
      wg_wait<0>();
      fence_regs(accq);
      uint32_t X0[4], X1[4];
#pragma unroll
      for (int c = 0; c < 3; c++) {
        X0[c] = pack_bf16(accq[4 * c], accq[4 * c + 1]);
        X1[c] = pack_bf16(accq[4 * c + 2], accq[4 * c + 3]);
      }
      X0[3] = pack_bf16(accq[24], 0.f);
      X1[3] = pack_bf16(accq[26], 0.f);
      float gl[14];
#pragma unroll
      for (int i = 0; i < 12; i++) gl[i] = accq[12 + i];
      s = (q & 1) ? accq[25] + accq[27] : 0.f;
      gl[12] = (q & 1) ? 0.f : accq[25];
      gl[13] = (q & 1) ? 0.f : accq[27];
      float acc[16];
#pragma unroll 1
      for (int l = 0; l < 3; l++) {
        mbar_wait(bars + (BAR_L2 + l) * 8, 0);
        LLoop<0>::run(acc, X0, X1, P0, P1, descL + (uint64_t)(l * WL_STEPS * 64));
        if (l == 2 && tl == 0)
          load_p(P0, P1, E0, E1, i0 + (wg + 4) * (4 * NF * 4), i5 + (wg + 4) * (4 * NF * 4), i6 + (wg + 4) * (4 * NF * 4), tb);
        wg_wait<0>();
        fence_regs(acc);
        if (l < 2) {
#pragma unroll
          for (int c = 0; c < 4; c++) {
            X0[c] = pack_bf16(acc[4 * c], acc[4 * c + 1]);
            X1[c] = pack_bf16(acc[4 * c + 2], acc[4 * c + 3]);
          }
          s += acc[13] + acc[15];
        }
      }
      float s2 = acc[12] * gl[12], s3 = acc[14] * gl[13];
#pragma unroll
      for (int c = 0; c < 3; c++) {
        s = fmaf(acc[4 * c], gl[4 * c], s);
        s2 = fmaf(acc[4 * c + 1], gl[4 * c + 1], s2);
        s3 = fmaf(acc[4 * c + 2], gl[4 * c + 2], s3);
        s = fmaf(acc[4 * c + 3], gl[4 * c + 3], s);
      }
      s += s2 + s3;
      if (tl == 0) sA = s;
    }
    {
      const bool hi = lane & 16;
      float v = hi ? s : sA;
      v += __shfl_xor_sync(0xffffffffu, hi ? sA : s, 16);
      v += __shfl_xor_sync(0xffffffffu, v, 8);
      v += __shfl_xor_sync(0xffffffffu, v, 4);
      v += __shfl_xor_sync(0xffffffffu, v, 2);
      v += __shfl_xor_sync(0xffffffffu, v, 1);
      if ((lane & 15) == 0) res[4 * wg + wq + (hi ? 16 : 0)] = v;
    }
    if (wg == 0) {
      const int row = cta * 32 + ((tid & 127) >> 2);
      unsigned long long x;
      int it = 0;
      do {
        asm volatile("ld.relaxed.gpu.global.u64 %0, [%1];" : "=l"(x) : "l"(scr.xchg + row * 4 + q) : "memory");
      } while ((unsigned)(x >> 32) != epoch && ++it < (1 << 22));
      float v = __uint_as_float((unsigned)x);
      v += __shfl_xor_sync(0xffffffffu, v, 1);
      v += __shfl_xor_sync(0xffffffffu, v, 2);
      if (q == 0) res[32 + ((tid & 127) >> 2)] = v + bf_ld(bout);
    }
    __syncthreads();
    if (warp == 0) out[cta * 32 + lane] = __float2bfloat16(res[lane] + res[32 + lane]);
  }
}

typedef CUresult (*EncodeFn)(CUtensorMap*, CUtensorMapDataType, cuuint32_t, void*, const cuuint64_t*, const cuuint64_t*,
                             const cuuint32_t*, const cuuint32_t*, CUtensorMapInterleave, CUtensorMapSwizzle,
                             CUtensorMapL2promotion, CUtensorMapFloatOOBfill);

}

extern "C" void kernel_launch(void* const* d_in, const int* in_sizes, int n_in, void* d_out, int out_size) {
  (void)in_sizes; (void)n_in; (void)out_size;
  const int* idx = (const int*)d_in[0];
  const __nv_bfloat16* table = (const __nv_bfloat16*)d_in[1];
  const __nv_bfloat16* ws = (const __nv_bfloat16*)d_in[2];
  const __nv_bfloat16* wc = (const __nv_bfloat16*)d_in[3];
  const __nv_bfloat16* w1 = (const __nv_bfloat16*)d_in[4];
  const __nv_bfloat16* b1 = (const __nv_bfloat16*)d_in[5];
  const __nv_bfloat16* w2 = (const __nv_bfloat16*)d_in[6];
  const __nv_bfloat16* bout = (const __nv_bfloat16*)d_in[7];

  static EncodeFn encode = nullptr;
  static Scratch scr;
  if (!encode) {
    cudaGetSymbolAddress((void**)&scr.img, g_img);
    cudaGetSymbolAddress((void**)&scr.cnt, g_cnt);
    cudaGetSymbolAddress((void**)&scr.xchg, g_xchg);
    void* fn = nullptr;
    cudaDriverEntryPointQueryResult qr;
    cudaGetDriverEntryPoint("cuTensorMapEncodeTiled", &fn, cudaEnableDefault, &qr);
    encode = (EncodeFn)fn;
    cudaFuncSetAttribute(xdeepfm_kernel, cudaFuncAttributeMaxDynamicSharedMemorySize, SMEM_BYTES);
  }
  CUtensorMap tmtab;
  {
    cuuint64_t dims[2] = {64, 250};
    cuuint64_t strides[1] = {128};
    cuuint32_t box[2] = {64, 64};
    cuuint32_t es[2] = {1, 1};
    encode(&tmtab, CU_TENSOR_MAP_DATA_TYPE_BFLOAT16, 2, (void*)table, dims, strides, box, es, CU_TENSOR_MAP_INTERLEAVE_NONE,
           CU_TENSOR_MAP_SWIZZLE_128B, CU_TENSOR_MAP_L2_PROMOTION_L2_128B, CU_TENSOR_MAP_FLOAT_OOB_FILL_NONE);
  }
  xdeepfm_kernel<<<NCTA, NTHR, SMEM_BYTES, cudaStreamPerThread>>>(ws, wc, idx, scr, w1, b1, w2, bout, (__nv_bfloat16*)d_out, tmtab);
}
```
